```python
import torch

def _softmax(x, axis=-1):
    return torch.softmax(x, dim=axis)
def _gelu(x):
    return torch.nn.functional.gelu(x, approximate="tanh")
def _silu(x):
    return torch.nn.functional.silu(x)
def _sigmoid(x):
    return torch.sigmoid(x)
def _layernorm(x, axis=-1, eps=1e-5):
    m = x.mean(dim=axis, keepdim=True)
    v = x.var(dim=axis, keepdim=True, unbiased=False)
    return (x - m) / torch.sqrt(v + eps)
def _scatter_add(tgt, idx, src, axis=0):
    return tgt.clone().index_add_(axis, idx, src)
def _segment_sum(src, seg, n):
    out = torch.zeros((n,) + src.shape[1:], dtype=src.dtype)
    return out.index_add_(0, seg, src)
def _pad(x, pw):
    flat = tuple(v for pair in reversed(pw) for v in pair)
    return torch.nn.functional.pad(x, flat)

kernel_name = 'parallel_sum__ssm_conv_h3__swiglu_ffn__prompt'

def setup_inputs():

    _w = (lambda a: (lambda t: t.to(torch.bfloat16) if t.is_floating_point() else t)(torch.as_tensor(a)))
    def _A_setup():
        B, S, D = 1, 2048, 1024
        ks = 4
        return {
            "q": _w((lambda *s: torch.randn(*s, dtype=torch.bfloat16) * 0.05)(B, S, D)),
            "k": _w((lambda *s: torch.randn(*s, dtype=torch.bfloat16) * 0.8)(B, S, D)),
            "v": _w((lambda *s: torch.randn(*s, dtype=torch.bfloat16) * 0.8)(B, S, D)),
            "shift_k": _w((lambda *s: torch.randn(*s, dtype=torch.bfloat16) * 0.8)(D, ks) * 0.5),
            "ssm_k": _w((lambda *s: torch.randn(*s, dtype=torch.bfloat16) * 0.8)(D, S) * (1.0 / S ** 0.5)),
            "ssm_D": _w((lambda *s: torch.randn(*s, dtype=torch.bfloat16) * 0.8)(D)),
        }
    _A_in = _A_setup()

    def _B_setup():
        B, S, D, F = 1, 2048, 1024, 3584
        return {
            "x": _w((lambda *s: torch.randn(*s, dtype=torch.bfloat16) * 0.05)(B, S, D)),
            "w_gate": _w((lambda *s: torch.randn(*s, dtype=torch.bfloat16) * 0.05)(D, F)),
            "w_up": _w((lambda *s: torch.randn(*s, dtype=torch.bfloat16) * 0.05)(D, F)),
            "w_down": _w((lambda *s: torch.randn(*s, dtype=torch.bfloat16) * 0.05)(F, D)),
        }
    _B_in = _B_setup()

    return {
        "A_q": _A_in["q"],
        "A_k": _A_in["k"],
        "A_v": _A_in["v"],
        "A_shift_k": _A_in["shift_k"],
        "A_ssm_k": _A_in["ssm_k"],
        "A_ssm_D": _A_in["ssm_D"],
        "B_x": _B_in["x"],
        "B_w_gate": _B_in["w_gate"],
        "B_w_up": _B_in["w_up"],
        "B_w_down": _B_in["w_down"],
    }

def reference(A_q, A_k, A_v, A_shift_k, A_ssm_k, A_ssm_D, B_x, B_w_gate, B_w_up, B_w_down):
    def _A_ref(q, k, v, shift_k, ssm_k, ssm_D):
        B, S, D = q.shape
        ks = shift_k.shape[-1]
        k_pad = _pad(k, ((0, 0), (ks - 1, 0), (0, 0)))
        k_shift = torch.zeros_like(k)
        for t in range(ks):
            k_shift = k_shift + k_pad[:, t:t + S, :] * shift_k[:, ks - 1 - t][None, None, :]
        kv = k_shift * v
        L = 2 * S
        kv_pad = _pad(kv, ((0, 0), (0, S), (0, 0)))
        kf_pad = _pad(ssm_k, ((0, 0), (0, S)))
        kv_f = (lambda x, axes=(-2,-1): torch.fft.rfft2(x.float(), dim=axes))(kv_pad[:, None, :, :], axes=(1, 2))
        kf_f = (lambda x, axes=(-2,-1): torch.fft.rfft2(x.float(), dim=axes))(kf_pad[:, None, :], axes=(1, 2))
        kf_f = (lambda x, *d: x.permute(*d))(kf_f, 1, 2, 0)
        y_f = kv_f * kf_f[None, :, :, :]
        y = (lambda x, s, axes=(-2,-1): torch.fft.irfft2(x, s=s, dim=axes).to(torch.bfloat16))(y_f, (1, L), axes=(1, 2))[:, 0, :S, :]
        y = y + kv * ssm_D[None, None, :]
        return q * y

    def _B_ref(x, w_gate, w_up, w_down):
        g = _silu(x @ w_gate)
        u = x @ w_up
        return (g * u) @ w_down

    x = A_q
    xn = _layernorm(x, axis=-1)
    return x + _A_ref(xn, A_k, A_v, A_shift_k, A_ssm_k, A_ssm_D) + _B_ref(xn, B_w_gate, B_w_up, B_w_down)
```

```cpp
#include <cuda_runtime.h>
#include <cuda_bf16.h>
#include <cuda.h>
#include <stdint.h>

namespace {

constexpr int SEQ = 2048, DM = 1024, FF = 3584;
constexpr int STAGES = 4;
constexpr uint32_t A_BYTES = 16384, B_BYTES = 32768, STAGE_BYTES = A_BYTES + B_BYTES;
constexpr uint32_t STG_OFF = STAGES * STAGE_BYTES;
constexpr uint32_t BAR_OFF = STG_OFF + 32768;
constexpr uint32_t FAC_OFF = BAR_OFF + 256;
constexpr uint32_t SMEM_ALLOC = 232448;
static_assert(FAC_OFF + 2048 <= SMEM_ALLOC, "smem");
constexpr int NTHREADS = 384;
constexpr int NMAIN = 128;
constexpr int NCTAS = 132;
#define KSPLIT 30

constexpr uint32_t U_CH = 5120;
constexpr uint32_t CV_H_OFF = 4 * U_CH;
constexpr uint32_t CV_D_OFF = 4 * U_CH + 4 * 4096;
constexpr uint32_t CV_Y_OFF = CV_D_OFF + 1024;
#define CONV_B 14
constexpr int CONV_C = (DM - 64 * CONV_B) / 4;
#define CONVA 3
constexpr int CONV_AFTER = CONVA;

constexpr uint32_t BAR_FULL = 0, BAR_EMPTY = 32, BAR_STGF = 64, BAR_STGE = 80, BAR_AUX = 96, BAR_COR = 112, BAR_CSL = 120, BAR_CSP = 128, BAR_LN = 160, BAR_ONE = 224, BAR_T0 = 248;

struct Flags {
  unsigned ln[32];
  unsigned h[16][32];
  unsigned u[32];
  unsigned y[32];
  unsigned done[32];
  unsigned csn[32];
};

__device__ __align__(1024) __nv_bfloat16 g_h[SEQ * FF];
__device__ __align__(1024) uint8_t g_u[DM * U_CH];
__device__ __align__(1024) Flags g_flags;
__device__ __align__(1024) float g_csp[8][8][256];
__device__ __align__(1024) uint2 g_stat[SEQ];

__device__ __forceinline__ uint32_t smem_u32(const void* p) { return (uint32_t)__cvta_generic_to_shared(p); }
__device__ __forceinline__ void mbar_init(uint32_t bar, uint32_t cnt) {
  asm volatile("mbarrier.init.shared::cta.b64 [%0], %1;" ::"r"(bar), "r"(cnt) : "memory");
}
__device__ __forceinline__ void mbar_expect_tx(uint32_t bar, uint32_t bytes) {
  asm volatile("mbarrier.arrive.expect_tx.shared::cta.b64 _, [%0], %1;" ::"r"(bar), "r"(bytes) : "memory");
}
__device__ __forceinline__ void mbar_arrive(uint32_t bar) {
  asm volatile("mbarrier.arrive.shared::cta.b64 _, [%0];" ::"r"(bar) : "memory");
}
__device__ __forceinline__ void mbar_arrive_cluster(uint32_t cluster_addr) {
  asm volatile("mbarrier.arrive.shared::cluster.b64 _, [%0];" ::"r"(cluster_addr) : "memory");
}
__device__ __forceinline__ uint32_t mapa(uint32_t addr, uint32_t rank) {
  uint32_t r;
  asm volatile("mapa.shared::cluster.u32 %0, %1, %2;" : "=r"(r) : "r"(addr), "r"(rank));
  return r;
}
__device__ __forceinline__ bool mbar_try(uint32_t bar, uint32_t parity) {
  uint32_t ok;
  asm volatile(
      "{\n.reg .pred p;\nmbarrier.try_wait.parity.shared::cta.b64 p, [%1], %2;\nselp.u32 %0, 1, 0, p;\n}\n"
      : "=r"(ok)
      : "r"(bar), "r"(parity)
      : "memory");
  return ok != 0;
}
__device__ __forceinline__ bool timed_out(uint32_t bar_any) {
  uint32_t now, t0;
  asm volatile("mov.u32 %0, %%globaltimer_lo;" : "=r"(now));
  asm volatile("ld.shared.u32 %0, [%1];" : "=r"(t0) : "r"((bar_any & ~255u) + BAR_T0));
  return (now - t0) > 2000000000u;
}
__device__ __forceinline__ void mbar_wait(uint32_t bar, uint32_t parity) {
  while (!mbar_try(bar, parity)) {
    if (timed_out(bar)) break;
  }
}
__device__ __forceinline__ unsigned ld_acquire(const unsigned* p) {
  unsigned v;
  asm volatile("ld.acquire.gpu.global.u32 %0, [%1];" : "=r"(v) : "l"(p) : "memory");
  return v;
}
__device__ __forceinline__ void red_release(unsigned* p, unsigned v) {
  asm volatile("red.release.gpu.global.add.u32 [%0], %1;" ::"l"(p), "r"(v) : "memory");
}
__device__ __forceinline__ void wait_flag(const unsigned* p, unsigned target, uint32_t bar_any) {
  while (ld_acquire(p) < target) {
    __nanosleep(32);
    if (timed_out(bar_any)) break;
  }
}
__device__ __forceinline__ void fence_proxy_async() { asm volatile("fence.proxy.async.global;" ::: "memory"); }
__device__ __forceinline__ void fence_proxy_async_smem() { asm volatile("fence.proxy.async.shared::cta;" ::: "memory"); }
__device__ __forceinline__ void bar_sync(int id, int n) { asm volatile("bar.sync %0, %1;" ::"r"(id), "r"(n) : "memory"); }
__device__ __forceinline__ void bar_arrive(int id, int n) { asm volatile("bar.arrive %0, %1;" ::"r"(id), "r"(n) : "memory"); }
__device__ __forceinline__ void cluster_sync_all() {
  asm volatile("barrier.cluster.arrive.relaxed;\nbarrier.cluster.wait;" ::: "memory");
}
__device__ __forceinline__ void tma_load_2d(uint32_t dst, const CUtensorMap* tm, int c0, int c1, uint32_t bar) {
  asm volatile(
      "cp.async.bulk.tensor.2d.shared::cluster.global.mbarrier::complete_tx::bytes [%0], [%1, {%3, %4}], [%2];" ::"r"(dst),
      "l"(tm), "r"(bar), "r"(c0), "r"(c1)
      : "memory");
}
__device__ __forceinline__ void tma_load_3d(uint32_t dst, const CUtensorMap* tm, int c0, int c1, int c2, uint32_t bar) {
  asm volatile(
      "cp.async.bulk.tensor.3d.shared::cluster.global.mbarrier::complete_tx::bytes [%0], [%1, {%3, %4, %5}], [%2];" ::"r"(dst),
      "l"(tm), "r"(bar), "r"(c0), "r"(c1), "r"(c2)
      : "memory");
}
__device__ __forceinline__ void tma_load_3d_mc(uint32_t dst, const CUtensorMap* tm, int c0, int c1, int c2, uint32_t bar,
                                               uint16_t mask) {
  asm volatile(
      "cp.async.bulk.tensor.3d.shared::cluster.global.mbarrier::complete_tx::bytes.multicast::cluster [%0], [%1, {%3, %4, "
      "%5}], [%2], %6;" ::"r"(dst),
      "l"(tm), "r"(bar), "r"(c0), "r"(c1), "r"(c2), "h"(mask)
      : "memory");
}
__device__ __forceinline__ uint64_t policy_evict_first() {
  uint64_t pol;
  asm volatile("createpolicy.fractional.L2::evict_first.b64 %0, 1.0;" : "=l"(pol));
  return pol;
}
__device__ __forceinline__ void tma_load_3d_mc_h(uint32_t dst, const CUtensorMap* tm, int c0, int c1, int c2, uint32_t bar,
                                                 uint16_t mask, uint64_t pol) {
  asm volatile(
      "cp.async.bulk.tensor.3d.shared::cluster.global.mbarrier::complete_tx::bytes.multicast::cluster.L2::cache_hint [%0], "
      "[%1, {%3, %4, %5}], [%2], %6, %7;" ::"r"(dst),
      "l"(tm), "r"(bar), "r"(c0), "r"(c1), "r"(c2), "h"(mask), "l"(pol)
      : "memory");
}
__device__ __forceinline__ void tma_load_2d_h(uint32_t dst, const CUtensorMap* tm, int c0, int c1, uint32_t bar, uint64_t pol) {
  asm volatile(
      "cp.async.bulk.tensor.2d.shared::cluster.global.mbarrier::complete_tx::bytes.L2::cache_hint [%0], [%1, {%3, %4}], [%2], "
      "%5;" ::"r"(dst),
      "l"(tm), "r"(bar), "r"(c0), "r"(c1), "l"(pol)
      : "memory");
}
__device__ __forceinline__ void bulk_load_h(uint32_t dst, const void* src, uint32_t bytes, uint32_t bar, uint64_t pol) {
  asm volatile("cp.async.bulk.shared::cluster.global.mbarrier::complete_tx::bytes.L2::cache_hint [%0], [%1], %2, [%3], %4;" ::"r"(dst),
               "l"(src), "r"(bytes), "r"(bar), "l"(pol)
               : "memory");
}
__device__ __forceinline__ uint32_t ldg32_ef(const void* p, uint64_t pol) {
  uint32_t v;
  asm volatile("ld.global.nc.L1::no_allocate.L2::cache_hint.u32 %0, [%1], %2;" : "=r"(v) : "l"(p), "l"(pol));
  return v;
}
__device__ __forceinline__ void tma_store_3d(const CUtensorMap* tm, int c0, int c1, int c2, uint32_t src) {
  asm volatile("cp.async.bulk.tensor.3d.global.shared::cta.bulk_group [%0, {%2, %3, %4}], [%1];" ::"l"(tm), "r"(src),
               "r"(c0), "r"(c1), "r"(c2)
               : "memory");
}
__device__ __forceinline__ void bulk_commit() { asm volatile("cp.async.bulk.commit_group;" ::: "memory"); }
__device__ __forceinline__ void bulk_wait_read0() { asm volatile("cp.async.bulk.wait_group.read 0;" ::: "memory"); }
__device__ __forceinline__ void bulk_wait0() { asm volatile("cp.async.bulk.wait_group 0;" ::: "memory"); }
__device__ __forceinline__ void prefetch_tmap(const CUtensorMap* tm) {
  asm volatile("prefetch.tensormap [%0];" ::"l"(tm) : "memory");
}
__device__ __forceinline__ void wgmma_fence() { asm volatile("wgmma.fence.sync.aligned;" ::: "memory"); }
__device__ __forceinline__ void wgmma_commit() { asm volatile("wgmma.commit_group.sync.aligned;" ::: "memory"); }
template <int N>
__device__ __forceinline__ void wgmma_wait() {
  asm volatile("wgmma.wait_group.sync.aligned %0;" ::"n"(N) : "memory");
}
template <int N>
__device__ __forceinline__ void fence_regs(float (&d)[N]) {
#pragma unroll
  for (int i = 0; i < N; ++i) asm volatile("" : "+f"(d[i])::"memory");
}
__device__ __forceinline__ void stmatrix_x4(uint32_t addr, uint32_t r0, uint32_t r1, uint32_t r2, uint32_t r3) {
  asm volatile("stmatrix.sync.aligned.m8n8.x4.shared.b16 [%0], {%1, %2, %3, %4};" ::"r"(addr), "r"(r0), "r"(r1), "r"(r2),
               "r"(r3)
               : "memory");
}
__device__ __forceinline__ void ldmatrix_x4(uint32_t addr, uint32_t& r0, uint32_t& r1, uint32_t& r2, uint32_t& r3) {
  asm volatile("ldmatrix.sync.aligned.m8n8.x4.shared.b16 {%0, %1, %2, %3}, [%4];"
               : "=r"(r0), "=r"(r1), "=r"(r2), "=r"(r3)
               : "r"(addr)
               : "memory");
}
__device__ __forceinline__ uint32_t lds32(uint32_t addr) {
  uint32_t v;
  asm volatile("ld.shared.u32 %0, [%1];" : "=r"(v) : "r"(addr) : "memory");
  return v;
}
__device__ __forceinline__ uint2 lds64(uint32_t addr) {
  uint2 v;
  asm volatile("ld.shared.v2.u32 {%0, %1}, [%2];" : "=r"(v.x), "=r"(v.y) : "r"(addr) : "memory");
  return v;
}
__device__ __forceinline__ uint4 lds128(uint32_t addr) {
  uint4 v;
  asm volatile("ld.shared.v4.u32 {%0, %1, %2, %3}, [%4];" : "=r"(v.x), "=r"(v.y), "=r"(v.z), "=r"(v.w) : "r"(addr) : "memory");
  return v;
}
__device__ __forceinline__ void sts32(uint32_t addr, uint32_t v) {
  asm volatile("st.shared.u32 [%0], %1;" ::"r"(addr), "r"(v) : "memory");
}
__device__ __forceinline__ void sts128(uint32_t addr, uint32_t a, uint32_t b, uint32_t c, uint32_t d) {
  asm volatile("st.shared.v4.u32 [%0], {%1, %2, %3, %4};" ::"r"(addr), "r"(a), "r"(b), "r"(c), "r"(d) : "memory");
}
__device__ __forceinline__ uint4 ldg_nc(const void* p) {
  uint4 v;
  asm volatile("ld.global.nc.L1::no_allocate.v4.u32 {%0, %1, %2, %3}, [%4];"
               : "=r"(v.x), "=r"(v.y), "=r"(v.z), "=r"(v.w)
               : "l"(p));
  return v;
}
__device__ __forceinline__ void stg128(void* p, uint32_t a, uint32_t b, uint32_t c, uint32_t d) {
  asm volatile("st.global.v4.u32 [%0], {%1, %2, %3, %4};" ::"l"(p), "r"(a), "r"(b), "r"(c), "r"(d) : "memory");
}
__device__ __forceinline__ uint32_t pack_bf16(float lo, float hi) {
  uint32_t r;
  asm("cvt.rn.bf16x2.f32 %0, %1, %2;" : "=r"(r) : "f"(hi), "f"(lo));
  return r;
}
__device__ __forceinline__ float bf_lo(uint32_t w) { return __uint_as_float(w << 16); }
__device__ __forceinline__ float bf_hi(uint32_t w) { return __uint_as_float(w & 0xffff0000u); }
__device__ __forceinline__ float round_bf16(float x) { return __bfloat162float(__float2bfloat16_rn(x)); }
__device__ __forceinline__ uint32_t bmul2(uint32_t a, uint32_t b) {
  uint32_t r;
  asm("mul.rn.bf16x2 %0, %1, %2;" : "=r"(r) : "r"(a), "r"(b));
  return r;
}
__device__ __forceinline__ uint32_t badd2(uint32_t a, uint32_t b) {
  uint32_t r;
  asm("add.rn.bf16x2 %0, %1, %2;" : "=r"(r) : "r"(a), "r"(b));
  return r;
}
__device__ __forceinline__ uint32_t bfma2(uint32_t a, uint32_t b, uint32_t c) {
  uint32_t r;
  asm("fma.rn.bf16x2 %0, %1, %2, %3;" : "=r"(r) : "r"(a), "r"(b), "r"(c));
  return r;
}
__device__ __forceinline__ void bulk_store(void* dst, uint32_t src, uint32_t bytes) {
  asm volatile("cp.async.bulk.global.shared::cta.bulk_group [%0], [%1], %2;" ::"l"(dst), "r"(src), "r"(bytes) : "memory");
}
__device__ __forceinline__ uint32_t prmt(uint32_t a, uint32_t b, uint32_t sel) { return __byte_perm(a, b, sel); }

__device__ __forceinline__ void mbar_arrive_cluster_n(uint32_t cluster_addr, uint32_t n) {
  asm volatile("mbarrier.arrive.shared::cluster.b64 _, [%0], %1;" ::"r"(cluster_addr), "r"(n) : "memory");
}
__device__ __forceinline__ void bulk_load(uint32_t dst, const void* src, uint32_t bytes, uint32_t bar) {
  asm volatile("cp.async.bulk.shared::cluster.global.mbarrier::complete_tx::bytes [%0], [%1], %2, [%3];" ::"r"(dst), "l"(src),
               "r"(bytes), "r"(bar)
               : "memory");
}
__device__ __forceinline__ void ldmatrix_x4_t(uint32_t addr, uint32_t& r0, uint32_t& r1, uint32_t& r2, uint32_t& r3) {
  asm volatile("ldmatrix.sync.aligned.m8n8.x4.trans.shared.b16 {%0, %1, %2, %3}, [%4];"
               : "=r"(r0), "=r"(r1), "=r"(r2), "=r"(r3)
               : "r"(addr)
               : "memory");
}
__device__ __forceinline__ uint32_t lds16(uint32_t addr) {
  uint16_t v;
  asm volatile("ld.shared.u16 %0, [%1];" : "=h"(v) : "r"(addr) : "memory");
  return v;
}
__device__ __forceinline__ void sts64(uint32_t addr, uint32_t a, uint32_t b) {
  asm volatile("st.shared.v2.u32 [%0], {%1, %2};" ::"r"(addr), "r"(a), "r"(b) : "memory");
}
__device__ __forceinline__ void red_publish(unsigned* p, unsigned v) {
  asm volatile("fence.proxy.async.global;\nred.release.gpu.global.add.u32 [%0], %1;" ::"l"(p), "r"(v) : "memory");
}
__device__ __forceinline__ void fence_acq_rel_gpu() { asm volatile("fence.acq_rel.gpu;" ::: "memory"); }

__device__ __forceinline__ void wgmma_ss_n256(float (&d)[128], uint64_t da, uint64_t db, int scale_d) {
  asm volatile(
    "{\n.reg .pred p;\nsetp.ne.b32 p, %130, 0;\n"
    "wgmma.mma_async.sync.aligned.m64n256k16.f32.bf16.bf16 "
    "{%0, %1, %2, %3, %4, %5, %6, %7, %8, %9, %10, %11, %12, %13, %14, %15, %16, %17, %18, %19, %20, %21, %22, %23, %24, %25, %26, %27, %28, %29, %30, %31, %32, %33, %34, %35, %36, %37, %38, %39, %40, %41, %42, %43, %44, %45, %46, %47, %48, %49, %50, %51, %52, %53, %54, %55, %56, %57, %58, %59, %60, %61, %62, %63, %64, %65, %66, %67, %68, %69, %70, %71, %72, %73, %74, %75, %76, %77, %78, %79, %80, %81, %82, %83, %84, %85, %86, %87, %88, %89, %90, %91, %92, %93, %94, %95, %96, %97, %98, %99, %100, %101, %102, %103, %104, %105, %106, %107, %108, %109, %110, %111, %112, %113, %114, %115, %116, %117, %118, %119, %120, %121, %122, %123, %124, %125, %126, %127}, %128, %129, p, 1, 1, 0, 1;\n}\n"
    : "+f"(d[0]), "+f"(d[1]), "+f"(d[2]), "+f"(d[3]), "+f"(d[4]), "+f"(d[5]), "+f"(d[6]), "+f"(d[7]), "+f"(d[8]), "+f"(d[9]), "+f"(d[10]), "+f"(d[11]), "+f"(d[12]), "+f"(d[13]), "+f"(d[14]), "+f"(d[15]), "+f"(d[16]), "+f"(d[17]), "+f"(d[18]), "+f"(d[19]), "+f"(d[20]), "+f"(d[21]), "+f"(d[22]), "+f"(d[23]), "+f"(d[24]), "+f"(d[25]), "+f"(d[26]), "+f"(d[27]), "+f"(d[28]), "+f"(d[29]), "+f"(d[30]), "+f"(d[31]), "+f"(d[32]), "+f"(d[33]), "+f"(d[34]), "+f"(d[35]), "+f"(d[36]), "+f"(d[37]), "+f"(d[38]), "+f"(d[39]), "+f"(d[40]), "+f"(d[41]), "+f"(d[42]), "+f"(d[43]), "+f"(d[44]), "+f"(d[45]), "+f"(d[46]), "+f"(d[47]), "+f"(d[48]), "+f"(d[49]), "+f"(d[50]), "+f"(d[51]), "+f"(d[52]), "+f"(d[53]), "+f"(d[54]), "+f"(d[55]), "+f"(d[56]), "+f"(d[57]), "+f"(d[58]), "+f"(d[59]), "+f"(d[60]), "+f"(d[61]), "+f"(d[62]), "+f"(d[63]), "+f"(d[64]), "+f"(d[65]), "+f"(d[66]), "+f"(d[67]), "+f"(d[68]), "+f"(d[69]), "+f"(d[70]), "+f"(d[71]), "+f"(d[72]), "+f"(d[73]), "+f"(d[74]), "+f"(d[75]), "+f"(d[76]), "+f"(d[77]), "+f"(d[78]), "+f"(d[79]), "+f"(d[80]), "+f"(d[81]), "+f"(d[82]), "+f"(d[83]), "+f"(d[84]), "+f"(d[85]), "+f"(d[86]), "+f"(d[87]), "+f"(d[88]), "+f"(d[89]), "+f"(d[90]), "+f"(d[91]), "+f"(d[92]), "+f"(d[93]), "+f"(d[94]), "+f"(d[95]), "+f"(d[96]), "+f"(d[97]), "+f"(d[98]), "+f"(d[99]), "+f"(d[100]), "+f"(d[101]), "+f"(d[102]), "+f"(d[103]), "+f"(d[104]), "+f"(d[105]), "+f"(d[106]), "+f"(d[107]), "+f"(d[108]), "+f"(d[109]), "+f"(d[110]), "+f"(d[111]), "+f"(d[112]), "+f"(d[113]), "+f"(d[114]), "+f"(d[115]), "+f"(d[116]), "+f"(d[117]), "+f"(d[118]), "+f"(d[119]), "+f"(d[120]), "+f"(d[121]), "+f"(d[122]), "+f"(d[123]), "+f"(d[124]), "+f"(d[125]), "+f"(d[126]), "+f"(d[127])
    : "l"(da), "l"(db), "r"(scale_d));
}

template <int OFF, int SCALE_D>
__device__ __forceinline__ void wgmma_rs_n32(float (&d)[16], uint32_t a0, uint32_t a1, uint32_t a2, uint32_t a3, uint32_t dlo) {
  asm volatile(
    "{\n.reg .pred p;\n.reg .b32 lo;\n.reg .b64 dsc;\nsetp.ne.b32 p, %22, 0;\nadd.u32 lo, %20, %21;\nmov.b64 dsc, {lo, 0xC0000010};\n"
    "wgmma.mma_async.sync.aligned.m64n32k16.f32.bf16.bf16 "
    "{%0, %1, %2, %3, %4, %5, %6, %7, %8, %9, %10, %11, %12, %13, %14, %15}, {%16, %17, %18, %19}, dsc, p, 1, 1, 0;\n}\n"
    : "+f"(d[0]), "+f"(d[1]), "+f"(d[2]), "+f"(d[3]), "+f"(d[4]), "+f"(d[5]), "+f"(d[6]), "+f"(d[7]), "+f"(d[8]), "+f"(d[9]), "+f"(d[10]), "+f"(d[11]), "+f"(d[12]), "+f"(d[13]), "+f"(d[14]), "+f"(d[15])
    : "r"(a0), "r"(a1), "r"(a2), "r"(a3), "r"(dlo), "n"(OFF), "n"(SCALE_D));
}

__device__ __forceinline__ void wgmma_rs_n256_tb(float (&d)[128], uint32_t a0, uint32_t a1, uint32_t a2, uint32_t a3, uint64_t db, int scale_d) {
  asm volatile(
    "{\n.reg .pred p;\nsetp.ne.b32 p, %133, 0;\n"
    "wgmma.mma_async.sync.aligned.m64n256k16.f32.bf16.bf16 "
    "{%0, %1, %2, %3, %4, %5, %6, %7, %8, %9, %10, %11, %12, %13, %14, %15, %16, %17, %18, %19, %20, %21, %22, %23, %24, %25, %26, %27, %28, %29, %30, %31, %32, %33, %34, %35, %36, %37, %38, %39, %40, %41, %42, %43, %44, %45, %46, %47, %48, %49, %50, %51, %52, %53, %54, %55, %56, %57, %58, %59, %60, %61, %62, %63, %64, %65, %66, %67, %68, %69, %70, %71, %72, %73, %74, %75, %76, %77, %78, %79, %80, %81, %82, %83, %84, %85, %86, %87, %88, %89, %90, %91, %92, %93, %94, %95, %96, %97, %98, %99, %100, %101, %102, %103, %104, %105, %106, %107, %108, %109, %110, %111, %112, %113, %114, %115, %116, %117, %118, %119, %120, %121, %122, %123, %124, %125, %126, %127}, {%128, %129, %130, %131}, %132, p, 1, 1, 1;\n}\n"
    : "+f"(d[0]), "+f"(d[1]), "+f"(d[2]), "+f"(d[3]), "+f"(d[4]), "+f"(d[5]), "+f"(d[6]), "+f"(d[7]), "+f"(d[8]), "+f"(d[9]), "+f"(d[10]), "+f"(d[11]), "+f"(d[12]), "+f"(d[13]), "+f"(d[14]), "+f"(d[15]), "+f"(d[16]), "+f"(d[17]), "+f"(d[18]), "+f"(d[19]), "+f"(d[20]), "+f"(d[21]), "+f"(d[22]), "+f"(d[23]), "+f"(d[24]), "+f"(d[25]), "+f"(d[26]), "+f"(d[27]), "+f"(d[28]), "+f"(d[29]), "+f"(d[30]), "+f"(d[31]), "+f"(d[32]), "+f"(d[33]), "+f"(d[34]), "+f"(d[35]), "+f"(d[36]), "+f"(d[37]), "+f"(d[38]), "+f"(d[39]), "+f"(d[40]), "+f"(d[41]), "+f"(d[42]), "+f"(d[43]), "+f"(d[44]), "+f"(d[45]), "+f"(d[46]), "+f"(d[47]), "+f"(d[48]), "+f"(d[49]), "+f"(d[50]), "+f"(d[51]), "+f"(d[52]), "+f"(d[53]), "+f"(d[54]), "+f"(d[55]), "+f"(d[56]), "+f"(d[57]), "+f"(d[58]), "+f"(d[59]), "+f"(d[60]), "+f"(d[61]), "+f"(d[62]), "+f"(d[63]), "+f"(d[64]), "+f"(d[65]), "+f"(d[66]), "+f"(d[67]), "+f"(d[68]), "+f"(d[69]), "+f"(d[70]), "+f"(d[71]), "+f"(d[72]), "+f"(d[73]), "+f"(d[74]), "+f"(d[75]), "+f"(d[76]), "+f"(d[77]), "+f"(d[78]), "+f"(d[79]), "+f"(d[80]), "+f"(d[81]), "+f"(d[82]), "+f"(d[83]), "+f"(d[84]), "+f"(d[85]), "+f"(d[86]), "+f"(d[87]), "+f"(d[88]), "+f"(d[89]), "+f"(d[90]), "+f"(d[91]), "+f"(d[92]), "+f"(d[93]), "+f"(d[94]), "+f"(d[95]), "+f"(d[96]), "+f"(d[97]), "+f"(d[98]), "+f"(d[99]), "+f"(d[100]), "+f"(d[101]), "+f"(d[102]), "+f"(d[103]), "+f"(d[104]), "+f"(d[105]), "+f"(d[106]), "+f"(d[107]), "+f"(d[108]), "+f"(d[109]), "+f"(d[110]), "+f"(d[111]), "+f"(d[112]), "+f"(d[113]), "+f"(d[114]), "+f"(d[115]), "+f"(d[116]), "+f"(d[117]), "+f"(d[118]), "+f"(d[119]), "+f"(d[120]), "+f"(d[121]), "+f"(d[122]), "+f"(d[123]), "+f"(d[124]), "+f"(d[125]), "+f"(d[126]), "+f"(d[127])
    : "r"(a0), "r"(a1), "r"(a2), "r"(a3), "l"(db), "r"(scale_d));
}

__device__ __forceinline__ void wgmma_rs_n64_tb(float (&d)[32], uint32_t a0, uint32_t a1, uint32_t a2, uint32_t a3, uint64_t db, int scale_d) {
  asm volatile(
    "{\n.reg .pred p;\nsetp.ne.b32 p, %37, 0;\n"
    "wgmma.mma_async.sync.aligned.m64n64k16.f32.bf16.bf16 "
    "{%0, %1, %2, %3, %4, %5, %6, %7, %8, %9, %10, %11, %12, %13, %14, %15, %16, %17, %18, %19, %20, %21, %22, %23, %24, %25, %26, %27, %28, %29, %30, %31}, {%32, %33, %34, %35}, %36, p, 1, 1, 1;\n}\n"
    : "+f"(d[0]), "+f"(d[1]), "+f"(d[2]), "+f"(d[3]), "+f"(d[4]), "+f"(d[5]), "+f"(d[6]), "+f"(d[7]), "+f"(d[8]), "+f"(d[9]), "+f"(d[10]), "+f"(d[11]), "+f"(d[12]), "+f"(d[13]), "+f"(d[14]), "+f"(d[15]), "+f"(d[16]), "+f"(d[17]), "+f"(d[18]), "+f"(d[19]), "+f"(d[20]), "+f"(d[21]), "+f"(d[22]), "+f"(d[23]), "+f"(d[24]), "+f"(d[25]), "+f"(d[26]), "+f"(d[27]), "+f"(d[28]), "+f"(d[29]), "+f"(d[30]), "+f"(d[31])
    : "r"(a0), "r"(a1), "r"(a2), "r"(a3), "l"(db), "r"(scale_d));
}

constexpr uint64_t DESC_A = (1ull << 62) | (64ull << 32) | (1ull << 16);
constexpr uint64_t DESC_B = (1ull << 62) | (64ull << 32) | (512ull << 16);
constexpr uint64_t DESC_C = (1ull << 62) | (64ull << 32) | (128ull << 16);

struct Pipe {
  uint32_t stage, phase;
  __device__ __forceinline__ void advance() {
    if (++stage == STAGES) { stage = 0; phase ^= 1; }
  }
};

template <bool FIRST>
__device__ __forceinline__ void gemm_kstep(float (&acc)[128], uint32_t sbase, int wg, Pipe& ps, uint32_t empty_cl, bool sig) {
  mbar_wait(sbase + BAR_OFF + BAR_FULL + 8 * ps.stage, ps.phase);
  const uint32_t sa = sbase + ps.stage * STAGE_BYTES;
  const uint64_t da = DESC_A | (uint64_t)(((sa + wg * 8192) & 0x3FFFF) >> 4);
  const uint64_t db = DESC_B | (uint64_t)(((sa + A_BYTES) & 0x3FFFF) >> 4);
  wgmma_fence();
  wgmma_ss_n256(acc, da, db, FIRST ? 0 : 1);
  wgmma_ss_n256(acc, da + 2, db + 128, 1);
  wgmma_ss_n256(acc, da + 4, db + 256, 1);
  wgmma_ss_n256(acc, da + 6, db + 384, 1);
  wgmma_commit();
  if (!FIRST) {
    wgmma_wait<1>();
    if (sig) mbar_arrive_cluster(empty_cl + 8 * ((ps.stage + STAGES - 1) % STAGES));
  }
  ps.advance();
}

template <bool CSFIRST>
__device__ __forceinline__ void gemm_kstep_cs(float (&acc)[128], float (&cs)[32], const uint32_t (&one)[4], int chunk,
                                              uint32_t sbase, int wg, Pipe& ps, uint32_t empty_cl, bool sig) {
  mbar_wait(sbase + BAR_OFF + BAR_FULL + 8 * ps.stage, ps.phase);
  const uint32_t sa = sbase + ps.stage * STAGE_BYTES;
  const uint64_t da = DESC_A | (uint64_t)(((sa + wg * 8192) & 0x3FFFF) >> 4);
  const uint64_t db = DESC_B | (uint64_t)(((sa + A_BYTES) & 0x3FFFF) >> 4);
  wgmma_fence();
  wgmma_ss_n256(acc, da, db, 1);
  wgmma_ss_n256(acc, da + 2, db + 128, 1);
  wgmma_ss_n256(acc, da + 4, db + 256, 1);
  wgmma_ss_n256(acc, da + 6, db + 384, 1);
  const uint64_t dc = db + chunk * 512;
  wgmma_rs_n64_tb(cs, one[0], one[1], one[2], one[3], dc, CSFIRST ? 0 : 1);
  wgmma_rs_n64_tb(cs, one[0], one[1], one[2], one[3], dc + 128, 1);
  wgmma_rs_n64_tb(cs, one[0], one[1], one[2], one[3], dc + 256, 1);
  wgmma_rs_n64_tb(cs, one[0], one[1], one[2], one[3], dc + 384, 1);
  wgmma_commit();
  wgmma_wait<1>();
  if (sig) mbar_arrive_cluster(empty_cl + 8 * ((ps.stage + STAGES - 1) % STAGES));
  ps.advance();
}

__device__ __forceinline__ uint32_t silu_mul2(uint32_t g2, uint32_t u2) {
  const float h0 = 0.5f * bf_lo(g2), h1 = 0.5f * bf_hi(g2);
  float t0, t1;
  asm("tanh.approx.f32 %0, %1;" : "=f"(t0) : "f"(h0));
  asm("tanh.approx.f32 %0, %1;" : "=f"(t1) : "f"(h1));
  return bmul2(pack_bf16(fmaf(h0, t0, h0), fmaf(h1, t1, h1)), u2);
}
template <int C>
__device__ __forceinline__ void epi_chunk(const uint32_t (&pk)[64], uint32_t stg, uint32_t sx) {
#pragma unroll
  for (int j = 4 * C; j < 4 * C + 4; j += 2)
    stmatrix_x4(stg + (j >> 3) * 8192 + ((sx ^ (j & 7)) << 4), silu_mul2(pk[2 * j], pk[32 + 2 * j]),
                silu_mul2(pk[2 * j + 1], pk[33 + 2 * j]), silu_mul2(pk[2 * j + 2], pk[34 + 2 * j]),
                silu_mul2(pk[2 * j + 3], pk[35 + 2 * j]));
}

template <int G, int S>
__device__ __forceinline__ void conv_shift(float (&d)[4][16], const uint32_t (&a)[16], uint32_t dlo) {
  constexpr int NB = 4 - (G >> 1), O = 32 * (G & 1) + 8 * S, SC = (G | S) != 0;
  wgmma_rs_n32<O, SC>(d[0], a[4 * S], a[4 * S + 1], a[4 * S + 2], a[4 * S + 3], dlo);
  if (NB > 1) wgmma_rs_n32<O + 64, SC>(d[1], a[4 * S], a[4 * S + 1], a[4 * S + 2], a[4 * S + 3], dlo);
  if (NB > 2) wgmma_rs_n32<O + 128, SC>(d[2], a[4 * S], a[4 * S + 1], a[4 * S + 2], a[4 * S + 3], dlo);
  if (NB > 3) wgmma_rs_n32<O + 192, SC>(d[3], a[4 * S], a[4 * S + 1], a[4 * S + 2], a[4 * S + 3], dlo);
}
template <int G>
__device__ __forceinline__ void conv_group(float (&d)[4][16], const uint32_t (&a)[16], uint32_t dlo) {
  wgmma_fence();
  conv_shift<G, 0>(d, a, dlo);
  conv_shift<G, 1>(d, a, dlo);
  conv_shift<G, 2>(d, a, dlo);
  conv_shift<G, 3>(d, a, dlo);
  wgmma_commit();
}
template <bool FIRST>
__device__ __forceinline__ void conv_load_a(uint32_t (&a)[16], uint32_t addr, int y0, uint32_t dval) {
#pragma unroll
  for (int s = 0; s < 4; ++s) {
    uint32_t w0 = lds32(addr + s * 128), w1 = lds32(addr + s * 128 + 4), w2 = lds32(addr + s * 128 + 8);
    if (FIRST && s == 0) {
      w0 = (y0 >= 0) ? w0 : 0u;
      w1 = (y0 >= -1) ? w1 : 0u;
      w2 = (y0 >= -2) ? w2 : 0u;
      w0 = (y0 == 0) ? badd2(w0, dval) : w0;
      w1 = (y0 == -1) ? badd2(w1, dval) : w1;
      w2 = (y0 == -2) ? badd2(w2, dval) : w2;
    }
    a[4 * s + 0] = prmt(w0, w1, 0x5432);
    a[4 * s + 1] = w1;
    a[4 * s + 2] = prmt(w1, w2, 0x5432);
    a[4 * s + 3] = w2;
  }
#pragma unroll
  for (int i = 0; i < 16; ++i) asm volatile("" : "+r"(a[i])::"memory");
}

struct Params {
  const __nv_bfloat16* x;
  const __nv_bfloat16* k;
  const __nv_bfloat16* v;
  const __nv_bfloat16* shift_k;
  const __nv_bfloat16* ssm_k;
  const __nv_bfloat16* ssm_d;
  const __nv_bfloat16* w_gate;
  const __nv_bfloat16* w_up;
  __nv_bfloat16* out;
};

__device__ __forceinline__ void mma_bf16(float (&c)[4], uint32_t a0, uint32_t a1, uint32_t a2, uint32_t a3, uint32_t b0,
                                         uint32_t b1) {
  asm("mma.sync.aligned.m16n8k16.row.col.f32.bf16.bf16.f32 {%0, %1, %2, %3}, {%4, %5, %6, %7}, {%8, %9}, {%0, %1, %2, %3};"
      : "+f"(c[0]), "+f"(c[1]), "+f"(c[2]), "+f"(c[3])
      : "r"(a0), "r"(a1), "r"(a2), "r"(a3), "r"(b0), "r"(b1));
}
__device__ __forceinline__ void mma_bf16_k8(float (&c)[4], uint32_t a0, uint32_t a1, uint32_t b0) {
  asm("mma.sync.aligned.m16n8k8.row.col.f32.bf16.bf16.f32 {%0, %1, %2, %3}, {%4, %5}, {%6}, {%0, %1, %2, %3};"
      : "+f"(c[0]), "+f"(c[1]), "+f"(c[2]), "+f"(c[3])
      : "r"(a0), "r"(a1), "r"(b0));
}
__device__ __forceinline__ void ln_rows(uint4 (&xin)[4][4], uint32_t dst, int lane, uint32_t stat) {
  uint4 xv[2][4];
  uint32_t z;
  int npass;
  asm volatile("mov.u32 %0, 0;\nmov.u32 %1, 3;" : "=r"(z), "=r"(npass));
#pragma unroll
  for (int i = 0; i < 8; ++i) xv[i >> 2][i & 3] = make_uint4(z, z, z, z);
  const bool diag = (lane & 3) == (lane >> 3);
#pragma unroll 1
  for (int pass = 0; pass < npass; ++pass) {
    float sum[2], sq[2];
#pragma unroll
    for (int rr = 0; rr < 2; ++rr) {
      float s[4] = {0.f, 0.f, 0.f, 0.f}, qa[4] = {0.f, 0.f, 0.f, 0.f}, qb[4] = {0.f, 0.f, 0.f, 0.f};
      float qc[4] = {0.f, 0.f, 0.f, 0.f}, qd[4] = {0.f, 0.f, 0.f, 0.f};
#pragma unroll
      for (int i = 0; i < 4; ++i) {
        const uint4 v = xv[rr][i];
        mma_bf16(s, v.x, v.y, v.z, v.w, 0x3F803F80u, 0x3F803F80u);
        mma_bf16_k8(qa, v.x, v.y, v.x);
        mma_bf16_k8(qb, v.x, v.y, v.y);
        mma_bf16_k8(qc, v.z, v.w, v.z);
        mma_bf16_k8(qd, v.z, v.w, v.w);
      }
      sum[rr] = s[0] + s[2];
      const float e0 = (qa[0] + qb[2]) + (qc[0] + qd[2]), e1 = (qa[1] + qb[3]) + (qc[1] + qd[3]);
      sq[rr] = diag ? ((lane & 4) ? e1 : e0) : 0.f;
    }
#pragma unroll
    for (int o = 16; o > 0; o >>= 1)
#pragma unroll
      for (int rr = 0; rr < 2; ++rr) {
        if (o >= 4) sum[rr] += __shfl_xor_sync(0xffffffffu, sum[rr], o);
        sq[rr] += __shfl_xor_sync(0xffffffffu, sq[rr], o);
      }
#pragma unroll
    for (int rr = 0; rr < 2; ++rr) {
      const float mean = sum[rr] * (1.0f / DM);
      const uint32_t nm = pack_bf16(-mean, -mean);
      const float vb = round_bf16(fmaxf(fmaf(-mean, mean, sq[rr] * (1.0f / DM)), 0.f));
      float sd;
      asm("sqrt.approx.f32 %0, %1;" : "=f"(sd) : "f"(round_bf16(vb + 1e-5f)));
      float rden;
      asm("rcp.approx.f32 %0, %1;" : "=f"(rden) : "f"(round_bf16(sd)));
      if (lane == 0) sts64(stat + rr * 8, nm, __float_as_uint(rden));
#pragma unroll
      for (int i = 0; i < 4; ++i) {
        const uint32_t w[4] = {xv[rr][i].x, xv[rr][i].y, xv[rr][i].z, xv[rr][i].w};
        uint32_t o[4];
#pragma unroll
        for (int c = 0; c < 4; ++c) {
          const uint32_t d = badd2(w[c], nm);
          o[c] = pack_bf16(bf_lo(d) * rden, bf_hi(d) * rden);
        }
        sts128(dst + rr * 2048 + i * 512, o[0], o[1], o[2], o[3]);
      }
    }
#pragma unroll
    for (int i = 0; i < 8; ++i) xv[i >> 2][i & 3] = xin[i >> 2][i & 3];
#pragma unroll
    for (int i = 0; i < 8; ++i) xin[i >> 2][i & 3] = xin[2 + (i >> 2)][i & 3];
    if (pass) {
      dst += 4096;
      stat += 16;
    }
  }
}

__device__ __forceinline__ void kv_helper(const Params& p, int it, int rb, int lane) {
  const uint64_t ef = policy_evict_first();
  const int ch0 = it * 64 + lane * 2;
  const int t0 = rb * 16;
  uint32_t kr[19], vr[16];
  const __nv_bfloat16* kp = p.k + (size_t)t0 * DM + ch0;
  const __nv_bfloat16* vp = p.v + (size_t)t0 * DM + ch0;
  const uint4 w = ldg_nc(p.shift_k + (size_t)ch0 * 4);
  kr[0] = kr[1] = kr[2] = 0u;
  if (rb > 0) {
#pragma unroll
    for (int i = 0; i < 3; ++i) kr[i] = ldg32_ef(kp + (i - 3) * DM, ef);
  }
#pragma unroll
  for (int i = 0; i < 16; ++i) kr[i + 3] = ldg32_ef(kp + i * DM, ef);
#pragma unroll
  for (int i = 0; i < 16; ++i) vr[i] = ldg32_ef(vp + i * DM, ef);
  __syncwarp();
  const uint32_t s0 = prmt(w.x, w.z, 0x5410), s1 = prmt(w.x, w.z, 0x7632), s2 = prmt(w.y, w.w, 0x5410),
                 s3 = prmt(w.y, w.w, 0x7632);
#pragma unroll
  for (int i = 0; i < 16; ++i) {
    uint32_t s = bmul2(kr[i], s3);
    s = badd2(s, bmul2(kr[i + 1], s2));
    s = badd2(s, bmul2(kr[i + 2], s1));
    s = badd2(s, bmul2(kr[i + 3], s0));
    vr[i] = bmul2(s, vr[i]);
  }
  const bool odd = lane & 1;
  uint32_t own[8], oth[8];
#pragma unroll
  for (int i = 0; i < 8; ++i) {
    const int ra = 4 * (i >> 1) + 2 + (i & 1), rb_ = 4 * (i >> 1) + (i & 1);
    own[i] = odd ? vr[rb_] : vr[ra];
    oth[i] = __shfl_xor_sync(0xffffffffu, odd ? vr[ra] : vr[rb_], 1);
  }
  const int nu = 127 - rb;
  uint8_t* ud = g_u + (size_t)(ch0 & ~3) * U_CH + nu * 32 + ((((nu >> 2) ^ lane) & 1) << 4);
#pragma unroll
  for (int c = 0; c < 4; ++c) {
    const uint32_t sel = (c & 1) ? 0x7632 : 0x5410;
    uint32_t o[4];
#pragma unroll
    for (int i = 0; i < 4; ++i) {
      const uint32_t lo = ((c >> 1) != 0) == odd ? own[2 * i] : oth[2 * i];
      const uint32_t hi = ((c >> 1) != 0) == odd ? own[2 * i + 1] : oth[2 * i + 1];
      o[i] = prmt(hi, lo, sel);
    }
    stg128(ud + c * U_CH, o[0], o[1], o[2], o[3]);
  }
  if (lane < 28) stg128(g_u + (size_t)(it * 64 + (rb >> 1)) * U_CH + 4096 + (rb & 1) * 448 + lane * 16, 0, 0, 0, 0);
}

__device__ __forceinline__ void conv_phase(uint32_t sbase, int wg, int w, int lane, Pipe& ps, uint32_t& ev, int ncc, int ch0) {
  const uint32_t bars = sbase + BAR_OFF;
  const int g = lane >> 2, q = lane & 3;
  const int gp = g & 1, g0 = (g >> 1) & 1, g1 = g >> 2;
  const int y0 = 8 * (g >> 1) + 2 * w + gp - 2 * q - 2;
  const int src1 = g0 ? (lane - 8) : (((lane + 8) & ~3) | ((q + 1) & 3));
  const int src2 = g1 ? (((lane - 16) & ~3) | ((q - 1) & 3)) : (((lane + 16) & ~3) | ((q + 1) & 3));
  const bool r1_shift = g0 && (q == 0);
  const bool keep_odd = g1 || (q == 3);
  const int off = (g1 ? (6 + 2 * q) : (q < 3 ? 2 * q : 14)) + (1 - g0);
  const int nl = 15 - off;
  const uint32_t yo_e = (nl >> 2) * 128 + (((2 * (nl & 3) + (w >> 1)) ^ (nl >> 2)) << 4) + (w & 1) * 8 + gp * 4;
  if (wg == 1) bar_arrive(2, 256);
#pragma unroll 1
  for (int cc = 0; cc < ncc; ++cc) {
    if ((cc & 1) == 0) mbar_wait(bars + BAR_FULL + 8 * ps.stage, ps.phase);
    const int slot = (cc & 1) * 2 + wg;
    const int chs = ch0 + (cc >> 1) * 4;
    const uint32_t sa = sbase + ps.stage * STAGE_BYTES;
    const uint32_t hb = sa + CV_H_OFF + slot * 4096;
    const uint32_t ha = hb + y0 * 4;
    uint32_t a0[16], a1[16], a2[16], a3[16], a4[16], a5[16];
    uint32_t a6[16];
    conv_load_a<true>(a0, ha, y0, lds16(sa + CV_D_OFF + (chs - min(chs & ~7, DM - 16) + slot) * 2));
    conv_load_a<false>(a1, ha + 512, 0, 0);
    conv_load_a<false>(a2, ha + 1024, 0, 0);
    conv_load_a<false>(a3, ha + 1536, 0, 0);
    conv_load_a<false>(a4, ha + 2048, 0, 0);
    conv_load_a<false>(a5, ha + 2560, 0, 0);
    conv_load_a<false>(a6, ha + 3072, 0, 0);
    const uint32_t dv = (((sa + slot * U_CH) & 0x3FFFF) >> 4) | 0x10000u;
    const uint32_t du0 = __shfl_sync(0xffffffffu, dv, 0), du1 = __shfl_sync(0xffffffffu, dv + 64, 0),
                   du2 = __shfl_sync(0xffffffffu, dv + 128, 0), du3 = __shfl_sync(0xffffffffu, dv + 192, 0);
    float d[4][16];
    bar_sync(2 + wg, 256);
    conv_group<0>(d, a0, du0);
    conv_group<1>(d, a1, du0);
    conv_group<2>(d, a2, du1);
    conv_group<3>(d, a3, du1);
    conv_group<4>(d, a4, du2);
    conv_group<5>(d, a5, du2);
    conv_group<6>(d, a6, du3);
    if (!(wg == 1 && cc == ncc - 1)) bar_arrive(3 - wg, 256);
    wgmma_wait<6>();
    conv_load_a<false>(a0, ha + 3584, 0, 0);
    conv_group<7>(d, a0, du3);
    wgmma_wait<0>();
    fence_regs(d[0]);
    fence_regs(d[1]);
    fence_regs(d[2]);
    fence_regs(d[3]);
    float v[17][2];
#pragma unroll
    for (int j = 0; j < 16; ++j)
#pragma unroll
      for (int i = 0; i < 2; ++i) {
        const float nxt = (j < 15) ? d[((j + 1) >> 2) & 3][4 * ((j + 1) & 3) + 2 * i] : 0.f;
        const float snd = r1_shift ? nxt : d[j >> 2][4 * (j & 3) + 2 * i];
        v[j][i] = d[j >> 2][4 * (j & 3) + 2 * i + 1] + __shfl_sync(0xffffffffu, snd, src1);
      }
    v[16][0] = v[16][1] = 0.f;
    uint32_t yw[8];
#pragma unroll
    for (int jj = 0; jj < 8; ++jj) {
      float o[2];
#pragma unroll
      for (int i = 0; i < 2; ++i) {
        const float sa_ = q ? v[2 * jj][i] : v[2 * jj + 2][i];
        const float sb_ = (q < 3) ? v[2 * jj + 1][i] : v[2 * jj][i];
        const float snd = g1 ? sa_ : sb_;
        const float kp = keep_odd ? v[2 * jj + 1][i] : v[2 * jj][i];
        o[i] = kp + __shfl_sync(0xffffffffu, snd, src2);
      }
      yw[jj] = pack_bf16(o[0], o[1]);
    }
    mbar_wait(bars + BAR_STGE + 8 * wg, (ev & 1) ^ 1);
#pragma unroll
    for (int jj = 0; jj < 8; ++jj) sts32(sa + CV_Y_OFF + wg * 4096 + (7 - jj) * 512 + (yo_e ^ (((7 - jj) & 1) << 6)), yw[jj]);
    fence_proxy_async_smem();
    mbar_arrive(bars + BAR_STGF + 8 * wg);
    ++ev;
    if ((cc & 1) || cc == ncc - 1) ps.advance();
  }
}

__device__ __forceinline__ int tile_nt(bool typeB, int ti, int q4) {
  const int grp = CONV_AFTER == 3 ? 2 * ti + (typeB ? 1 : 0) : (typeB ? (ti == 2 ? 6 : 2 * ti + 1) : (ti == 3 ? 5 : 2 * ti));
  return 4 * grp + q4;
}

__global__ void __cluster_dims__(2, 1, 1) __launch_bounds__(NTHREADS, 1)
fused_kernel(const __grid_constant__ CUtensorMap tm_x, const __grid_constant__ CUtensorMap tm_xn,
             const __grid_constant__ CUtensorMap tm_wg,
             const __grid_constant__ CUtensorMap tm_wu, const __grid_constant__ CUtensorMap tm_hst,
             const __grid_constant__ CUtensorMap tm_hld, const __grid_constant__ CUtensorMap tm_wd,
             const __grid_constant__ CUtensorMap tm_xn2, const __grid_constant__ CUtensorMap tm_x2,
             const __grid_constant__ CUtensorMap tm_yst, const __grid_constant__ CUtensorMap tm_yld,
             const __grid_constant__ CUtensorMap tm_out2, const __grid_constant__ CUtensorMap tm_out16, const Params p) {
  extern __shared__ uint8_t smem_raw[];
  const uint32_t sbase = (smem_u32(smem_raw) + 1023u) & ~1023u;
  const int tid = threadIdx.x, lane = tid & 31;
  const int warp0 = __shfl_sync(0xffffffffu, tid >> 5, 0);
  const int cl = blockIdx.x >> 1, rank = blockIdx.x & 1;
  const bool typeC = blockIdx.x >= NMAIN;
  const bool typeB = (cl & 1) != 0 || typeC;
  const int idx = cl >> 1;
  const int mp = idx & 7, q4 = idx >> 3;
  const int mb = 2 * mp + rank;
  const int rb = mb * 8 + (typeB ? 4 : 0) + q4;
  const int ntiles = typeB ? 3 : 4;
  const int ncc = (typeC ? CONV_C : CONV_B) / 2;
  const int ch0 = typeC ? 64 * CONV_B + ((int)blockIdx.x - NMAIN) * CONV_C : (idx * 2 + rank) * CONV_B;
  const uint32_t bars = sbase + BAR_OFF;

  uint4 xv[4][4];
  if (warp0 >= 4 && warp0 < 8 && !typeC) {
    const __nv_bfloat16* xp = p.x + (size_t)(rb * 16 + (warp0 - 4) * 4) * DM + lane * 8;
#pragma unroll
    for (int rr = 0; rr < 4; ++rr)
#pragma unroll
      for (int i = 0; i < 4; ++i) xv[rr][i] = ldg_nc(xp + rr * DM + i * 256);
  }
  if (tid == 256) {
    for (int s = 0; s < STAGES; ++s) {
      mbar_init(bars + BAR_FULL + 8 * s, 1);
      mbar_init(bars + BAR_EMPTY + 8 * s, 16);
    }
    for (int i = 0; i < 2; ++i) {
      mbar_init(bars + BAR_STGF + 8 * i, 128);
      mbar_init(bars + BAR_STGE + 8 * i, 1);
      mbar_init(bars + BAR_AUX + 8 * i, 1);
      mbar_init(bars + BAR_CSP + 8 * i, 4);
    }
    mbar_init(bars + BAR_COR, 32);
    mbar_init(bars + BAR_CSL, 1);
    mbar_init(bars + BAR_LN, 256);
    {
      uint32_t now;
      asm volatile("mov.u32 %0, %%globaltimer_lo;" : "=r"(now));
      sts32(bars + BAR_T0, now);
      sts128(bars + BAR_ONE, 0x3F803F80u, 0x3F803F80u, 0x3F803F80u, 0x3F803F80u);
    }
    asm volatile("fence.mbarrier_init.release.cluster;" ::: "memory");
    asm volatile("fence.acq_rel.cta;" ::: "memory");
  }
  __syncwarp();
  asm volatile("barrier.cluster.arrive.relaxed;" ::: "memory");
  if (warp0 >= 4 && warp0 < 8 && !typeC) {
    ln_rows(xv, sbase + STG_OFF + (warp0 - 4) * 8192 + lane * 16, lane, sbase + FAC_OFF + (warp0 - 4) * 32);
    fence_proxy_async_smem();
  }
  asm volatile("barrier.cluster.wait;" ::: "memory");

  if (warp0 >= 8) {
    asm volatile("setmaxnreg.dec.sync.aligned.u32 56;");
    const int warp = warp0;
    if (warp == 8) {
      Pipe ps{0, 0};
      const bool l0 = lane == 0;
      const CUtensorMap* tmb = rank ? &tm_wu : &tm_wg;
      uint32_t ready = 0, aflag = 0;
      const uint64_t ef = policy_evict_first();
      auto poll = [&]() {
        const unsigned v = ld_acquire(&g_flags.h[mb][lane]);
        ready = __ballot_sync(0xffffffffu, v >= 2);
        aflag = __shfl_sync(0xffffffffu, v, 28 + q4);
        if (l0) fence_proxy_async();
        return __any_sync(0xffffffffu, timed_out(bars));
      };
#pragma unroll 1
      for (int ti = typeC ? CONV_AFTER : 0; ti <= ntiles; ++ti) {
        const int nt = tile_nt(typeB, ti, q4);
        const CUtensorMap* tma = ti ? &tm_xn : &tm_x;
        if (ti == 1) {
          wait_flag(&g_flags.ln[mb], 8, bars);
          fence_proxy_async();
        }
        if (typeB && ti == CONV_AFTER) {
          wait_flag(&g_flags.u[0], 3 * NMAIN, bars);
          fence_proxy_async();
#pragma unroll 1
          for (int cc = 0; cc < ncc; cc += 2) {
            mbar_wait(bars + BAR_EMPTY + 8 * ps.stage, ps.phase ^ 1);
            if (l0) {
              const uint32_t fb = bars + BAR_FULL + 8 * ps.stage, sa = sbase + ps.stage * STAGE_BYTES;
              const int ch = ch0 + cc * 2, n = cc + 1 < ncc ? 4 : 2;
              mbar_expect_tx(fb, n * (4096 + U_CH) + 32);
              bulk_load_h(sa + CV_H_OFF, p.ssm_k + (size_t)ch * SEQ, n * 4096, fb, ef);
              bulk_load(sa, g_u + (size_t)ch * U_CH, n * U_CH, fb);
              bulk_load(sa + CV_D_OFF, p.ssm_d + min(ch & ~7, DM - 16), 32, fb);
            }
            ps.advance();
          }
          if (typeC) break;
        }
        if (ti == ntiles) break;
#pragma unroll 1
        for (int kb = 0; kb < 16; ++kb) {
          mbar_wait(bars + BAR_EMPTY + 8 * ps.stage, ps.phase ^ 1);
          if (l0) {
            const uint32_t fb = bars + BAR_FULL + 8 * ps.stage, sa = sbase + ps.stage * STAGE_BYTES;
            int kp = kb >> 1;
            if (ti == 0) kp = kp == 1 ? mp : (kp - (kp > 1) + (kp - (kp > 1) >= mp));
            const int kc = (2 * kp + (kb & 1)) * 64;
            mbar_expect_tx(fb, STAGE_BYTES);
            if (ti) tma_load_3d_mc_h(sa + A_BYTES + rank * 16384, tmb, 0, kc, 2 * nt, fb, 3, ef);
            else tma_load_3d_mc(sa + A_BYTES + rank * 16384, tmb, 0, kc, 2 * nt, fb, 3);
            tma_load_2d(sa, tma, kc, mb * 128, fb);
          }
          ps.advance();
        }
      }
      const int k2_beg = typeB ? KSPLIT : 0, k2_end = typeB ? (FF / 64) : KSPLIT;
      if (!typeC) {
#pragma unroll 1
      for (int kb = k2_beg; kb < k2_end; ++kb) {
        while (!((ready >> (kb >> 1)) & 1)) {
          if (poll()) break;
        }
        mbar_wait(bars + BAR_EMPTY + 8 * ps.stage, ps.phase ^ 1);
        if (l0) {
          const uint32_t fb = bars + BAR_FULL + 8 * ps.stage, sa = sbase + ps.stage * STAGE_BYTES;
          mbar_expect_tx(fb, STAGE_BYTES);
          tma_load_3d_mc_h(sa + A_BYTES + rank * 16384, &tm_wd, 0, kb * 64, q4 * 4 + rank * 2, fb, 3, ef);
          tma_load_2d_h(sa, &tm_hld, kb * 64, mb * 128, fb, ef);
        }
        ps.advance();
      }
      mbar_wait(bars + BAR_AUX, 0);
      mbar_wait(bars + BAR_AUX + 8, 0);
      poll();
      while ((ready & 0x0fffffffu) != 0x0fffffffu) {
        if (poll()) break;
      }
#pragma unroll 1
      for (int i = 0; i < 2; ++i) {
        mbar_wait(bars + BAR_EMPTY + 8 * ps.stage, ps.phase ^ 1);
        const uint32_t fb = bars + BAR_FULL + 8 * ps.stage, sa = sbase + ps.stage * STAGE_BYTES;
        const int row = mb * 128 + i * 64;
        if (l0) {
          mbar_expect_tx(fb, STAGE_BYTES);
          if (!typeB) tma_load_2d(sa + 32768, &tm_yld, row, q4 * 256, fb);
          else tma_load_3d(sa + 32768, &tm_x2, 0, row, q4 * 4, fb);
        }
        while (typeB && ((aflag >> (4 * i)) & 15) != 4) {
          if (poll()) break;
        }
        if (l0) {
          const CUtensorMap* tm = typeB ? &tm_out2 : &tm_xn2;
          tma_load_3d(sa, tm, 0, row, q4 * 4, fb);
          tma_load_3d(sa + 16384, tm, 0, row, q4 * 4 + 2, fb);
        }
        ps.advance();
      }
      }
      unsigned last = 0;
      if (l0) {
        fence_acq_rel_gpu();
        last = (atomicAdd(&g_flags.done[0], 1) == gridDim.x - 1);
        fence_acq_rel_gpu();
      }
      last = __shfl_sync(0xffffffffu, last, 0);
      if (last) {
        uint4* f = reinterpret_cast<uint4*>(&g_flags);
        for (int i = lane; i < (int)(sizeof(Flags) / 16); i += 32) f[i] = make_uint4(0, 0, 0, 0);
      }
    } else {
      if (!typeC) {
      if (warp == 10 && lane == 0) {
        mbar_wait(bars + BAR_LN, 0);
        bulk_store(p.out + (size_t)rb * 16 * DM, sbase + STG_OFF, 32768);
        bulk_store(g_stat + rb * 16, sbase + FAC_OFF, 128);
        bulk_commit();
        bulk_wait0();
        red_publish(&g_flags.ln[mb], 1);
      }
      __syncwarp();
      if (warp == 9) mbar_wait(bars + BAR_FULL + 8 * (STAGES - 1), 0);
      if (warp == 11) {
        const int nt0 = tile_nt(typeB, 0, q4);
        if (lane == 0) {
          mbar_wait(bars + BAR_CSP, 0);
          mbar_wait(bars + BAR_CSP + 8, 0);
          bulk_store(&g_csp[nt0][mp][rank * 128], sbase + FAC_OFF + 1024, 512);
          bulk_commit();
          wait_flag(&g_flags.ln[mb], 8, bars);
          bulk_wait0();
          red_publish(&g_flags.csn[nt0], 1);
          while (ld_acquire(&g_flags.csn[nt0]) < 16) {
            if (timed_out(bars)) break;
          }
          fence_proxy_async();
          mbar_expect_tx(bars + BAR_CSL, 8192 + 1024);
          bulk_load(sbase + STG_OFF + 8192, &g_csp[nt0][0][0], 8192, bars + BAR_CSL);
          bulk_load(sbase + STG_OFF + 16384, g_stat + mb * 128, 1024, bars + BAR_CSL);
        }
        __syncwarp();
        mbar_wait(bars + BAR_CSL, 0);
        float r[8];
#pragma unroll
        for (int i = 0; i < 8; ++i) r[i] = 0.f;
#pragma unroll
        for (int c = 0; c < 8; ++c) {
          const uint4 c0 = lds128(sbase + STG_OFF + 8192 + c * 1024 + lane * 32),
                      c1 = lds128(sbase + STG_OFF + 8192 + c * 1024 + lane * 32 + 16);
          r[0] += __uint_as_float(c0.x); r[1] += __uint_as_float(c0.y); r[2] += __uint_as_float(c0.z); r[3] += __uint_as_float(c0.w);
          r[4] += __uint_as_float(c1.x); r[5] += __uint_as_float(c1.y); r[6] += __uint_as_float(c1.z); r[7] += __uint_as_float(c1.w);
        }
        const uint32_t cb = sbase + STG_OFF + (lane >> 3) * 2048;
#pragma unroll
        for (int k = 0; k < 16; ++k) {
          uint32_t o[4] = {0, 0, 0, 0};
          if (k < 3) {
#pragma unroll
            for (int i = 0; i < 4; ++i) {
              o[i] = pack_bf16(r[2 * i], r[2 * i + 1]);
              r[2 * i] -= bf_lo(o[i]);
              r[2 * i + 1] -= bf_hi(o[i]);
            }
          }
          sts128(cb + k * 128 + (((lane ^ k) & 7) << 4), o[0], o[1], o[2], o[3]);
        }
        fence_proxy_async_smem();
        mbar_arrive(bars + BAR_COR);
      }
#pragma unroll 1
      for (int it = warp == 9 ? 0 : (warp == 10 ? 7 : 13); it < (warp == 9 ? 7 : (warp == 10 ? 13 : 16)); ++it) kv_helper(p, it, rb, lane);
      __syncwarp();
      if (lane == 0) red_release(&g_flags.u[0], 1);
      if (warp == 11 && lane == 0) {
        prefetch_tmap(&tm_hld);
        prefetch_tmap(&tm_wd);
        prefetch_tmap(&tm_out2);
        prefetch_tmap(&tm_out16);
        prefetch_tmap(typeB ? &tm_x2 : &tm_xn2);
        prefetch_tmap(typeB ? &tm_yst : &tm_yld);
      }
      }
      if (warp <= 10 && lane == 0) {
        const int wg = warp - 9;
        const int nev = typeC ? ncc : (typeB ? 3 + ncc : 4);
#pragma unroll 1
        for (int ev = 0; ev < nev; ++ev) {
          mbar_wait(bars + BAR_STGF + 8 * wg, ev & 1);
          unsigned* flag;
          const int cc = typeC ? ev : ev - CONV_AFTER;
          if (!typeB || cc < 0 || cc >= ncc) {
            const int nt = tile_nt(typeB, (typeB && cc >= 0) ? ev - ncc : ev, q4);
            tma_store_3d(&tm_hst, 0, mb * 128 + wg * 64, 2 * nt, sbase + STG_OFF + wg * 16384);
            flag = &g_flags.h[mb][nt];
            bulk_commit();
            bulk_wait_read0();
          } else {
            const int slot = (cc & 1) * 2 + wg;
            const int stage = (cc >> 1) % STAGES;
            const int ch = ch0 + (cc >> 1) * 4 + slot;
            tma_store_3d(&tm_yst, 0, 0, ch, sbase + stage * STAGE_BYTES + CV_Y_OFF + wg * 4096);
            flag = &g_flags.y[ch >> 8];
            bulk_commit();
            bulk_wait_read0();
            if ((cc & 1) || cc == ncc - 1) {
              mbar_arrive_cluster_n(mapa(bars + BAR_EMPTY + 8 * stage, 0), 4);
              mbar_arrive_cluster_n(mapa(bars + BAR_EMPTY + 8 * stage, 1), 4);
            }
          }
          mbar_arrive(bars + BAR_STGE + 8 * wg);
          bulk_wait0();
          red_publish(flag, 1);
        }
        const uint32_t ab = bars + BAR_AUX + 8 * wg, dst = sbase + STG_OFF + wg * 16384;
        if (!typeB) {
          wait_flag(&g_flags.y[q4], 256, bars);
          fence_proxy_async();
          mbar_expect_tx(ab, 16384);
          tma_load_2d(dst, &tm_yld, mb * 128 + wg * 64, q4 * 256 + 128, ab);
        } else if (!typeC) {
          mbar_expect_tx(ab, 16384);
          tma_load_3d(dst, &tm_x2, 0, mb * 128 + wg * 64, q4 * 4 + 2, ab);
        }
      }
      __syncwarp();
    }
    cluster_sync_all();
  } else {
    asm volatile("setmaxnreg.inc.sync.aligned.u32 224;");
    const int warp = tid >> 5;
    const int wg = warp0 >> 2, w = warp & 3;
    const uint32_t empty_cl = mapa(bars + BAR_EMPTY, lane & 1);
    const bool sig = lane < 2;
    Pipe ps{0, 0};
    uint32_t ev = 0;
    const uint32_t rowoff = (16 * w + 8 * ((lane >> 3) & 1) + (lane & 7)) * 128;
    const uint32_t sx = (lane & 7) ^ (lane >> 4);
    const uint32_t stg = sbase + STG_OFF + wg * 16384 + rowoff;
    float acc[128];
    uint32_t pk[64];
    if (!typeC) {
      uint32_t one[4];
      asm volatile("ld.volatile.shared.v4.u32 {%0, %1, %2, %3}, [%4];"
                   : "=r"(one[0]), "=r"(one[1]), "=r"(one[2]), "=r"(one[3])
                   : "r"(bars + BAR_ONE)
                   : "memory");
      mbar_arrive(bars + BAR_LN);
      gemm_kstep<true>(acc, sbase, wg, ps, empty_cl, sig);
      gemm_kstep<false>(acc, sbase, wg, ps, empty_cl, sig);
      float cs[32];
      gemm_kstep_cs<true>(acc, cs, one, 2 * rank + wg, sbase, wg, ps, empty_cl, sig);
      gemm_kstep_cs<false>(acc, cs, one, 2 * rank + wg, sbase, wg, ps, empty_cl, sig);
      gemm_kstep<false>(acc, sbase, wg, ps, empty_cl, sig);
      fence_regs(cs);
      {
        if ((tid & 127) < 4) {
#pragma unroll
          for (int j = 0; j < 8; ++j)
            sts64(sbase + FAC_OFF + 1024 + wg * 256 + j * 32 + lane * 8, __float_as_uint(cs[4 * j]),
                  __float_as_uint(cs[4 * j + 1]));
          fence_proxy_async_smem();
          mbar_arrive(bars + BAR_CSP + 8 * wg);
        }
        __syncwarp();
      }
#pragma unroll 1
      for (int kb = 5; kb < 16; ++kb) gemm_kstep<false>(acc, sbase, wg, ps, empty_cl, sig);
      mbar_wait(bars + BAR_COR, 0);
      const uint32_t fa = sbase + STG_OFF + 16384 + (wg * 64 + 16 * w + (lane >> 2)) * 8;
      const uint2 st0 = lds64(fa), st1 = lds64(fa + 64);
      const uint32_t msk = (lane & 3) == 0 ? 0xffffffffu : ((lane & 3) == 1 ? 0x0000ffffu : 0u);
      uint32_t a0 = st0.x & msk, a1 = st1.x & msk, a2 = 0, a3 = 0;
      asm volatile("" : "+r"(a0), "+r"(a1), "+r"(a2), "+r"(a3)::"memory");
      wgmma_fence();
      wgmma_rs_n256_tb(acc, a0, a1, a2, a3, DESC_C | (uint64_t)(((sbase + STG_OFF) & 0x3FFFF) >> 4), 1);
      wgmma_commit();
      wgmma_wait<0>();
      if (sig) mbar_arrive_cluster(empty_cl + 8 * ((ps.stage + STAGES - 1) % STAGES));
      fence_regs(acc);
#pragma unroll
      for (int i = 0; i < 64; ++i) {
        const float rs = __uint_as_float((i & 1) ? st1.y : st0.y);
        pk[i] = pack_bf16(acc[2 * i] * rs, acc[2 * i + 1] * rs);
      }
    }
    bool pending = !typeC;
    {
#pragma unroll 1
    for (int item = typeC ? CONV_AFTER : 1; item < 5; ++item) {
      const bool is_conv = typeB && item == CONV_AFTER;
      const int nk = item == 4 ? (typeB ? (FF / 64 - KSPLIT) : KSPLIT) : 16;
      if (!is_conv) gemm_kstep<true>(acc, sbase, wg, ps, empty_cl, sig);
      if (pending) {
        if (item == 1) bar_sync(1, 256);
        mbar_wait(bars + BAR_STGE + 8 * wg, (ev & 1) ^ 1);
        epi_chunk<0>(pk, stg, sx);
      }
      if (!is_conv) gemm_kstep<false>(acc, sbase, wg, ps, empty_cl, sig);
      if (pending) epi_chunk<1>(pk, stg, sx);
      if (!is_conv) gemm_kstep<false>(acc, sbase, wg, ps, empty_cl, sig);
      if (pending) epi_chunk<2>(pk, stg, sx);
      if (!is_conv) gemm_kstep<false>(acc, sbase, wg, ps, empty_cl, sig);
      if (pending) {
        epi_chunk<3>(pk, stg, sx);
        fence_proxy_async_smem();
        mbar_arrive(bars + BAR_STGF + 8 * wg);
        ++ev;
      }
      if (is_conv) {
        wgmma_wait<0>();
        conv_phase(sbase, wg, w, lane, ps, ev, ncc, ch0);
        pending = false;
#pragma unroll
        for (int i = 0; i < 64; ++i) pk[i] = 0;
#pragma unroll
        for (int i = 0; i < 128; ++i) acc[i] = 0.f;
        if (typeC) break;
        continue;
      }
#pragma unroll 1
      for (int kb = 4; kb < nk; ++kb) {
        bool sg = sig;
        if (wg == 1 && kb == nk - 2) {
          wgmma_wait<0>();
          if (sig) mbar_arrive_cluster(empty_cl + 8 * ((ps.stage + STAGES - 1) % STAGES));
          sg = false;
          bar_sync(6, 256);
        }
        gemm_kstep<false>(acc, sbase, wg, ps, empty_cl, sg);
      }
      if (wg == 0) bar_arrive(6, 256);
      wgmma_wait<0>();
      if (sig) mbar_arrive_cluster(empty_cl + 8 * ((ps.stage + STAGES - 1) % STAGES));
      fence_regs(acc);
#pragma unroll
      for (int i = 0; i < 64; ++i) pk[i] = pack_bf16(acc[2 * i], acc[2 * i + 1]);
      pending = true;
    }
    if (!typeC) {
      if (wg == 1) ps.advance();
      mbar_wait(bars + BAR_FULL + 8 * ps.stage, ps.phase);
      mbar_wait(bars + BAR_AUX + 8 * wg, 0);
      const uint32_t buf = sbase + ps.stage * STAGE_BYTES;
      const uint32_t aux0 = buf + 32768, aux1 = sbase + STG_OFF + wg * 16384;
      uint32_t tq;
      asm volatile("mov.u32 %0, %%tid.x;" : "=r"(tq));
      const uint32_t yl = (8 * ((tq >> 4) & 1) + (tq & 7)) * 128 + ((((tq >> 4) & 6) + ((tq >> 3) & 1)) ^ (tq & 7)) * 16;
      int nhf;
      asm volatile("mov.u32 %0, 2;" : "=r"(nhf));
#pragma unroll 1
      for (int hf = 0; hf < nhf; ++hf) {
        uint32_t r[32], y[32];
        const uint32_t ad = buf + hf * 16384 + rowoff, ax = hf ? aux1 : aux0;
#pragma unroll
        for (int j = 0; j < 16; j += 2)
          ldmatrix_x4(ad + (j >> 3) * 8192 + ((sx ^ (j & 7)) << 4), r[2 * j], r[2 * j + 1], r[2 * j + 2], r[2 * j + 3]);
        if (!typeB) {
#pragma unroll
          for (int j = 0; j < 16; j += 2) ldmatrix_x4_t(ax + j * 1024 + yl, y[2 * j], y[2 * j + 1], y[2 * j + 2], y[2 * j + 3]);
#pragma unroll
          for (int i = 0; i < 32; ++i) r[i] = bfma2(r[i], y[i], pk[i]);
        } else {
#pragma unroll
          for (int j = 0; j < 16; j += 2)
            ldmatrix_x4(ax + rowoff + (j >> 3) * 8192 + ((sx ^ (j & 7)) << 4), y[2 * j], y[2 * j + 1], y[2 * j + 2],
                        y[2 * j + 3]);
#pragma unroll
          for (int i = 0; i < 32; ++i) r[i] = badd2(badd2(r[i], y[i]), pk[i]);
        }
#pragma unroll
        for (int j = 0; j < 16; j += 2)
          stmatrix_x4(ad + (j >> 3) * 8192 + ((sx ^ (j & 7)) << 4), r[2 * j], r[2 * j + 1], r[2 * j + 2], r[2 * j + 3]);
        fence_proxy_async_smem();
        __syncwarp();
        if (lane == 0) {
          const uint32_t src = buf + hf * 16384 + ((tq >> 5) & 3) * 2048;
          tma_store_3d(&tm_out16, 0, mb * 128 + (tq >> 5) * 16, q4 * 4 + hf * 2, src);
          tma_store_3d(&tm_out16, 0, mb * 128 + (tq >> 5) * 16, q4 * 4 + hf * 2 + 1, src + 8192);
          bulk_commit();
        }
#pragma unroll
        for (int i = 0; i < 32; ++i) pk[i] = pk[32 + i];
      }
      if (lane == 0) {
        if (!typeB) {
          bulk_wait0();
          red_publish(&g_flags.h[mb][28 + q4], wg ? 16 : 1);
        } else {
          bulk_wait_read0();
        }
      }
    }
    }
    __syncwarp();
    cluster_sync_all();
  }
}

typedef CUresult (*EncodeFn)(CUtensorMap*, CUtensorMapDataType, cuuint32_t, void*, const cuuint64_t*, const cuuint64_t*,
                             const cuuint32_t*, const cuuint32_t*, CUtensorMapInterleave, CUtensorMapSwizzle,
                             CUtensorMapL2promotion, CUtensorMapFloatOOBfill);

void make_map_2d(EncodeFn enc, CUtensorMap* tm, const void* ptr, int rows, int cols, int box_rows) {
  cuuint64_t dims[2] = {(cuuint64_t)cols, (cuuint64_t)rows};
  cuuint64_t strides[1] = {(cuuint64_t)cols * 2};
  cuuint32_t box[2] = {64, (cuuint32_t)box_rows};
  cuuint32_t es[2] = {1, 1};
  enc(tm, CU_TENSOR_MAP_DATA_TYPE_BFLOAT16, 2, const_cast<void*>(ptr), dims, strides, box, es,
      CU_TENSOR_MAP_INTERLEAVE_NONE, CU_TENSOR_MAP_SWIZZLE_128B, CU_TENSOR_MAP_L2_PROMOTION_NONE,
      CU_TENSOR_MAP_FLOAT_OOB_FILL_NONE);
}
void make_map_3d(EncodeFn enc, CUtensorMap* tm, const void* ptr, int rows, int cols, int box_rows, int box_chunks) {
  cuuint64_t dims[3] = {64, (cuuint64_t)rows, (cuuint64_t)(cols / 64)};
  cuuint64_t strides[2] = {(cuuint64_t)cols * 2, 128};
  cuuint32_t box[3] = {64, (cuuint32_t)box_rows, (cuuint32_t)box_chunks};
  cuuint32_t es[3] = {1, 1, 1};
  enc(tm, CU_TENSOR_MAP_DATA_TYPE_BFLOAT16, 3, const_cast<void*>(ptr), dims, strides, box, es,
      CU_TENSOR_MAP_INTERLEAVE_NONE, CU_TENSOR_MAP_SWIZZLE_128B, CU_TENSOR_MAP_L2_PROMOTION_NONE,
      CU_TENSOR_MAP_FLOAT_OOB_FILL_NONE);
}

}

extern "C" void kernel_launch(void* const* d_in, const int* in_sizes, int n_in, void* d_out, int out_size) {
  (void)in_sizes; (void)n_in; (void)out_size;
  static EncodeFn enc = nullptr;
  static void *h_p = nullptr, *yt_p = nullptr;
  if (!enc) {
    void* fn = nullptr;
    cudaDriverEntryPointQueryResult st;
    cudaGetDriverEntryPoint("cuTensorMapEncodeTiled", &fn, cudaEnableDefault, &st);
    enc = (EncodeFn)fn;
    cudaGetSymbolAddress(&h_p, g_h);
    cudaGetSymbolAddress(&yt_p, g_u);
    cudaFuncSetAttribute(fused_kernel, cudaFuncAttributeMaxDynamicSharedMemorySize, SMEM_ALLOC);
  }
  CUtensorMap tm_x, tm_xn, tm_wg, tm_wu, tm_hst, tm_hld, tm_wd, tm_xn2, tm_x2, tm_yst, tm_yld, tm_out, tm_out16;
  void* xn_p = d_out;
  make_map_2d(enc, &tm_x, d_in[0], SEQ, DM, 128);
  make_map_2d(enc, &tm_xn, xn_p, SEQ, DM, 128);
  make_map_3d(enc, &tm_wg, d_in[7], DM, FF, 64, 2);
  make_map_3d(enc, &tm_wu, d_in[8], DM, FF, 64, 2);
  make_map_3d(enc, &tm_hst, h_p, SEQ, FF, 64, 2);
  make_map_2d(enc, &tm_hld, h_p, SEQ, FF, 128);
  make_map_3d(enc, &tm_wd, d_in[9], FF, DM, 64, 2);
  {
    cuuint64_t dims[3] = {64, 32, (cuuint64_t)DM};
    cuuint64_t strides[2] = {128, (cuuint64_t)U_CH};
    cuuint32_t box[3] = {64, 32, 1};
    cuuint32_t es[3] = {1, 1, 1};
    enc(&tm_yst, CU_TENSOR_MAP_DATA_TYPE_BFLOAT16, 3, yt_p, dims, strides, box, es, CU_TENSOR_MAP_INTERLEAVE_NONE,
        CU_TENSOR_MAP_SWIZZLE_128B, CU_TENSOR_MAP_L2_PROMOTION_NONE, CU_TENSOR_MAP_FLOAT_OOB_FILL_NONE);
  }
  make_map_3d(enc, &tm_xn2, xn_p, SEQ, DM, 64, 2);
  make_map_3d(enc, &tm_x2, d_in[0], SEQ, DM, 64, 2);
  make_map_2d(enc, &tm_yld, yt_p, DM, U_CH / 2, 128);
  make_map_3d(enc, &tm_out, d_out, SEQ, DM, 64, 2);
  make_map_3d(enc, &tm_out16, d_out, SEQ, DM, 16, 1);
  Params p;
  p.x = (const __nv_bfloat16*)d_in[0];
  p.k = (const __nv_bfloat16*)d_in[1];
  p.v = (const __nv_bfloat16*)d_in[2];
  p.shift_k = (const __nv_bfloat16*)d_in[3];
  p.ssm_k = (const __nv_bfloat16*)d_in[4];
  p.ssm_d = (const __nv_bfloat16*)d_in[5];
  p.w_gate = (const __nv_bfloat16*)d_in[7];
  p.w_up = (const __nv_bfloat16*)d_in[8];
  p.out = (__nv_bfloat16*)d_out;
  fused_kernel<<<NCTAS, NTHREADS, SMEM_ALLOC>>>(tm_x, tm_xn, tm_wg, tm_wu, tm_hst, tm_hld, tm_wd, tm_xn2, tm_x2, tm_yst, tm_yld,
                                                tm_out, tm_out16, p);
}
```
